```python
import torch

def _softmax(x, axis=-1):
    return torch.softmax(x, dim=axis)
def _gelu(x):
    return torch.nn.functional.gelu(x, approximate="tanh")
def _silu(x):
    return torch.nn.functional.silu(x)
def _sigmoid(x):
    return torch.sigmoid(x)
def _layernorm(x, axis=-1, eps=1e-5):
    m = x.mean(dim=axis, keepdim=True)
    v = x.var(dim=axis, keepdim=True, unbiased=False)
    return (x - m) / torch.sqrt(v + eps)
def _scatter_add(tgt, idx, src, axis=0):
    return tgt.clone().index_add_(axis, idx, src)
def _segment_sum(src, seg, n):
    out = torch.zeros((n,) + src.shape[1:], dtype=src.dtype)
    return out.index_add_(0, seg, src)
def _pad(x, pw):
    flat = tuple(v for pair in reversed(pw) for v in pair)
    return torch.nn.functional.pad(x, flat)

kernel_name = 'standalone__groupnorm__sampling'

def setup_inputs():

    _w = (lambda a: (lambda t: t.to(torch.bfloat16) if t.is_floating_point() else t)(torch.as_tensor(a)))
    B = 32
    G = 32
    cpg = max(1, 512 // G)
    C = G * cpg
    H, W = 32, 16
    return {
        "x": _w(abs((lambda *s: torch.randn(*s, dtype=torch.bfloat16) * 0.05)(B, C, H, W))),
        "g": _w((lambda *s: torch.randn(*s, dtype=torch.bfloat16) * 0.05)(C) + 1.0),
        "b": _w((lambda *s: torch.randn(*s, dtype=torch.bfloat16) * 0.4)(C)),
    }

def reference(x, g, b):
    G = 32
    B, C, H, W = x.shape[0], x.shape[1], x.shape[2], x.shape[3]
    xr = x.reshape(B, G, C // G, H, W)
    mu = xr.mean(axis=(2, 3, 4), keepdims=True)
    var = ((xr - mu) ** 2).mean(axis=(2, 3, 4), keepdims=True)
    xn = (xr - mu) / torch.sqrt(var + 1e-5)
    xn = xn.reshape(B, C, H, W)
    return xn * g[None, :, None, None] + b[None, :, None, None]
```

```cpp
#include <cuda_runtime.h>
#include <cuda_bf16.h>
#include <stdint.h>


constexpr int GROUP_ELEMS = 8192;
constexpr int HW = 512;
constexpr int CPG = 16;
constexpr int NGROUPS_PER_B = 32;
constexpr int THREADS = 256;

__device__ __forceinline__ float bf_lo(uint32_t v) { return __uint_as_float(v << 16); }
__device__ __forceinline__ float bf_hi(uint32_t v) { return __uint_as_float(v & 0xffff0000u); }
__device__ __forceinline__ uint32_t pack_bf(float lo, float hi) {
    uint32_t r;
    asm("cvt.rn.bf16x2.f32 %0, %1, %2;" : "=r"(r) : "f"(hi), "f"(lo));
    return r;
}

__global__ void __launch_bounds__(THREADS, 8)
gn_kernel(const uint4* __restrict__ x, const __nv_bfloat16* __restrict__ g,
          const __nv_bfloat16* __restrict__ b, uint4* __restrict__ out) {
    const int grp = blockIdx.x;
    const int t = threadIdx.x;
    const uint4* xp = x + (size_t)grp * (GROUP_ELEMS / 8) + t;
    uint4 v[4];
#pragma unroll
    for (int i = 0; i < 4; i++) v[i] = __ldcs(xp + i * THREADS);

    float s = 0.f;
#pragma unroll
    for (int i = 0; i < 4; i++) {
        s += bf_lo(v[i].x) + bf_hi(v[i].x) + bf_lo(v[i].y) + bf_hi(v[i].y);
        s += bf_lo(v[i].z) + bf_hi(v[i].z) + bf_lo(v[i].w) + bf_hi(v[i].w);
    }
    __shared__ float red[2][8];
#pragma unroll
    for (int o = 16; o > 0; o >>= 1) s += __shfl_xor_sync(0xffffffffu, s, o);
    if ((t & 31) == 0) red[0][t >> 5] = s;
    __syncthreads();
    float tot = 0.f;
#pragma unroll
    for (int i = 0; i < 8; i++) tot += red[0][i];
    const float mean = tot * (1.f / GROUP_ELEMS);
    float q = 0.f;
#pragma unroll
    for (int i = 0; i < 4; i++) {
        uint32_t w[4] = {v[i].x, v[i].y, v[i].z, v[i].w};
#pragma unroll
        for (int j = 0; j < 4; j++) {
            float a = bf_lo(w[j]) - mean, c = bf_hi(w[j]) - mean;
            q = fmaf(a, a, q);
            q = fmaf(c, c, q);
        }
    }
#pragma unroll
    for (int o = 16; o > 0; o >>= 1) q += __shfl_xor_sync(0xffffffffu, q, o);
    if ((t & 31) == 0) red[1][t >> 5] = q;
    __syncthreads();
    float qt = 0.f;
#pragma unroll
    for (int i = 0; i < 8; i++) qt += red[1][i];
    const float rstd = rsqrtf(qt * (1.f / GROUP_ELEMS) + 1e-5f);

    uint4* op = out + (size_t)grp * (GROUP_ELEMS / 8) + t;
    const int cbase = (grp & (NGROUPS_PER_B - 1)) * CPG;
#pragma unroll
    for (int i = 0; i < 4; i++) {
        const int c = cbase + i * 4 + (t >> 6);
        const float sc = __bfloat162float(g[c]) * rstd;
        const float sh = __bfloat162float(b[c]) - mean * sc;
        uint4 o;
        o.x = pack_bf(fmaf(bf_lo(v[i].x), sc, sh), fmaf(bf_hi(v[i].x), sc, sh));
        o.y = pack_bf(fmaf(bf_lo(v[i].y), sc, sh), fmaf(bf_hi(v[i].y), sc, sh));
        o.z = pack_bf(fmaf(bf_lo(v[i].z), sc, sh), fmaf(bf_hi(v[i].z), sc, sh));
        o.w = pack_bf(fmaf(bf_lo(v[i].w), sc, sh), fmaf(bf_hi(v[i].w), sc, sh));
        op[i * THREADS] = o;
    }
}

extern "C" void kernel_launch(void* const* d_in, const int* in_sizes, int n_in,
                              void* d_out, int out_size) {
    const uint4* x = (const uint4*)d_in[0];
    const __nv_bfloat16* g = (const __nv_bfloat16*)d_in[1];
    const __nv_bfloat16* b = (const __nv_bfloat16*)d_in[2];
    int ngroups = in_sizes[0] / GROUP_ELEMS;
    gn_kernel<<<ngroups, THREADS>>>(x, g, b, (uint4*)d_out);
}
```

```cpp
#include <cuda_runtime.h>
#include <cuda_bf16.h>
#include <stdint.h>

namespace {

constexpr int kGroupElems = 8192;
constexpr int kNumGroups = 1024;
constexpr float kEps = 1e-5f;

constexpr int kNS = 3;
constexpr int kND = 8 - kNS;
constexpr int kT1 = 1250;
constexpr int kDT = 310;
constexpr int kD0 = 300;
constexpr int kThr = 80;

struct Scratch {
    uint4 probe[2560];
    unsigned int epoch, claim, pad0[30];
    unsigned int info, pad1[31];
    unsigned int pad2[(65536 - 40960 - 256) / 4];
    uint4 slots[4096];
};
static_assert(sizeof(Scratch) == 131072, "scratch layout");
__device__ uint4 g_scratch[2 * sizeof(Scratch) / sizeof(uint4)];

__device__ __forceinline__ float bf_lo(uint32_t v) { return __uint_as_float(v << 16); }
__device__ __forceinline__ float bf_hi(uint32_t v) { return __uint_as_float(v & 0xffff0000u); }
__device__ __forceinline__ uint32_t pack_bf(float lo, float hi) {
    uint32_t r;
    asm("cvt.rn.bf16x2.f32 %0, %1, %2;" : "=r"(r) : "f"(hi), "f"(lo));
    return r;
}
__device__ __forceinline__ uint4 norm4(uint4 v, float sc, float sh) {
    uint4 o;
    o.x = pack_bf(fmaf(bf_lo(v.x), sc, sh), fmaf(bf_hi(v.x), sc, sh));
    o.y = pack_bf(fmaf(bf_lo(v.y), sc, sh), fmaf(bf_hi(v.y), sc, sh));
    o.z = pack_bf(fmaf(bf_lo(v.z), sc, sh), fmaf(bf_hi(v.z), sc, sh));
    o.w = pack_bf(fmaf(bf_lo(v.w), sc, sh), fmaf(bf_hi(v.w), sc, sh));
    return o;
}
__device__ __forceinline__ uint32_t clk() {
    uint32_t r;
    asm volatile("mov.u32 %0, %%clock;" : "=r"(r)::"memory");
    return r;
}
__device__ __forceinline__ uint32_t clk_after(uint32_t v) {
    uint32_t r;
    asm volatile("{ .reg .pred p; setp.eq.u32 p, %1, 0x7fc0dea1; @p mov.u32 %0, %%clock_hi; @!p mov.u32 %0, %%clock; }"
                 : "=r"(r) : "r"(v) : "memory");
    return r;
}
__device__ __forceinline__ uint32_t dep_zero(uint32_t v) { return v == 0x7fc0dea1u ? 4u : 0u; }
__device__ __forceinline__ void spin_until(uint32_t start, int cycles) {
    const uint32_t tgt = start + cycles;
    while ((int)(tgt - clk()) > 0) {}
}
__device__ __forceinline__ uint32_t tid_opaque() {
    uint32_t r;
    asm volatile("mov.u32 %0, %%tid.x;" : "=r"(r));
    return r;
}
__device__ __forceinline__ uint32_t opq(uint32_t v) {
    asm volatile("" : "+r"(v));
    return v;
}
template <typename T> __device__ __forceinline__ T* boff(T* p, uint32_t bytes) { return (T*)((char*)p + bytes); }
template <typename T> __device__ __forceinline__ const T* boff(const T* p, uint32_t bytes) { return (const T*)((const char*)p + bytes); }

__device__ __forceinline__ int race_ld(const char* pa, const char* pb) {
    uint32_t a0, b0, a1, b1;
    asm volatile("prefetch.global.L2 [%2];\n prefetch.global.L2 [%3];\n"
                 "ld.volatile.global.u32 %0, [%2];\n ld.volatile.global.u32 %1, [%3];"
                 : "=r"(a0), "=r"(b0) : "l"(pa), "l"(pb) : "memory");
    const uint32_t z = dep_zero(a0 ^ b0);
    asm volatile("ld.volatile.global.u32 %0, [%2+64];\n ld.volatile.global.u32 %1, [%3+64];"
                 : "=r"(a1), "=r"(b1) : "l"(pa + z), "l"(pb + z) : "memory");
    const uint32_t ta = clk_after(a1);
    const uint32_t tb = clk_after(b1);
    return (int)(tb - ta);
}
template <bool kFresh>
__device__ __forceinline__ int race_atom(char* pa, char* pb) {
    uint32_t a1, b1, z = 0;
    if (kFresh) {
        asm volatile("st.volatile.global.v4.u32 [%2], {%4,%4,%4,%4};\n st.volatile.global.v4.u32 [%2+16], {%4,%4,%4,%4};\n"
                     "st.volatile.global.v4.u32 [%3], {%4,%4,%4,%4};\n st.volatile.global.v4.u32 [%3+16], {%4,%4,%4,%4};\n"
                     "atom.relaxed.gpu.global.exch.b32 %0, [%2], 1;\n atom.relaxed.gpu.global.exch.b32 %1, [%3], 1;"
                     : "=r"(a1), "=r"(b1) : "l"(pa), "l"(pb), "r"(0) : "memory");
        z = dep_zero(a1 ^ b1);
    }
    asm volatile("atom.relaxed.gpu.global.exch.b32 %0, [%2+16], 2;\n atom.relaxed.gpu.global.exch.b32 %1, [%3+16], 2;"
                 : "=r"(a1), "=r"(b1) : "l"(pa + z), "l"(pb + z) : "memory");
    const uint32_t ta = clk_after(a1);
    const uint32_t tb = clk_after(b1);
    return (int)(tb - ta);
}

template <int NV>
__device__ __forceinline__ float warp_sums(const uint4 (&v)[NV], int lane) {
    float s0 = 0.f, s1 = 0.f, q0 = 0.f, q1 = 0.f;
#pragma unroll
    for (int i = 0; i < NV; i++) {
        const uint32_t wv[4] = {v[i].x, v[i].y, v[i].z, v[i].w};
#pragma unroll
        for (int j = 0; j < 4; j++) {
            const float a = bf_lo(wv[j]), c = bf_hi(wv[j]);
            s0 += a; s1 += c;
            q0 = fmaf(a, a, q0); q1 = fmaf(c, c, q1);
        }
    }
    const float s = s0 + s1, q = q0 + q1;
    const bool lo = lane < 16;
    float r = (lo ? s : q) + __shfl_xor_sync(0xffffffffu, lo ? q : s, 16);
    r += __shfl_xor_sync(0xffffffffu, r, 8);
    r += __shfl_xor_sync(0xffffffffu, r, 4);
    r += __shfl_xor_sync(0xffffffffu, r, 2);
    r += __shfl_xor_sync(0xffffffffu, r, 1);
    return r;
}

__device__ __noinline__ void exact_path(const uint4* __restrict__ x, const unsigned short* __restrict__ g,
                                        const unsigned short* __restrict__ b, uint4* __restrict__ out,
                                        uint32_t base, int nv) {
    const uint4* xg = x + (base & ~1023u) + (base & 31);
    float s = 0.f;
#pragma unroll 4
    for (int i = 0; i < 32; i++) {
        const uint4 u = __ldg(xg + i * 32);
        s += ((bf_lo(u.x) + bf_hi(u.x)) + (bf_lo(u.y) + bf_hi(u.y))) + ((bf_lo(u.z) + bf_hi(u.z)) + (bf_lo(u.w) + bf_hi(u.w)));
    }
#pragma unroll 1
    for (int o = 16; o > 0; o >>= 1) s += __shfl_xor_sync(0xffffffffu, s, o);
    const float mu = s * (1.f / kGroupElems);
    float a = 0.f;
#pragma unroll 4
    for (int i = 0; i < 32; i++) {
        const uint4 u = __ldg(xg + i * 32);
        const uint32_t wv[4] = {u.x, u.y, u.z, u.w};
#pragma unroll
        for (int j = 0; j < 4; j++) {
            const float d0 = bf_lo(wv[j]) - mu, d1 = bf_hi(wv[j]) - mu;
            a = fmaf(d0, d0, a);
            a = fmaf(d1, d1, a);
        }
    }
#pragma unroll 1
    for (int o = 16; o > 0; o >>= 1) a += __shfl_xor_sync(0xffffffffu, a, o);
    const float rstd = rsqrtf(a * (1.f / kGroupElems) + kEps);
#pragma unroll 1
    for (int i = 0; i < nv; i++) {
        const uint32_t k = base + i * 32, c = (k >> 6) & 511;
        const uint4 u = __ldg(x + k);
        const float sc = bf_lo(g[c]) * rstd, sh = bf_lo(b[c]);
        uint4 o;
        o.x = pack_bf(fmaf(bf_lo(u.x) - mu, sc, sh), fmaf(bf_hi(u.x) - mu, sc, sh));
        o.y = pack_bf(fmaf(bf_lo(u.y) - mu, sc, sh), fmaf(bf_hi(u.y) - mu, sc, sh));
        o.z = pack_bf(fmaf(bf_lo(u.z) - mu, sc, sh), fmaf(bf_hi(u.z) - mu, sc, sh));
        o.w = pack_bf(fmaf(bf_lo(u.w) - mu, sc, sh), fmaf(bf_hi(u.w) - mu, sc, sh));
        out[k] = o;
    }
}

__device__ __forceinline__ void load_chunk(uint4 (&v)[8], uint2& g4, uint2& b4, uint32_t base,
                                           const uint4* x, const uint2* g, const uint2* b) {
    const uint4* xp = boff(x, opq(base << 4));
    const uint32_t go = opq((base >> 5) & 0x3f8);
#pragma unroll
    for (int i = 0; i < 8; i++)
        asm volatile("ld.global.nc.L1::no_allocate.v4.u32 {%0,%1,%2,%3}, [%4];"
                     : "=r"(v[i].x), "=r"(v[i].y), "=r"(v[i].z), "=r"(v[i].w) : "l"(xp + i * 32));
    asm volatile("ld.global.nc.v2.u32 {%0,%1}, [%2];" : "=r"(g4.x), "=r"(g4.y) : "l"(boff(g, go)));
    asm volatile("ld.global.nc.v2.u32 {%0,%1}, [%2];" : "=r"(b4.x), "=r"(b4.y) : "l"(boff(b, go)));
}

__device__ __forceinline__ uint32_t group_class(uint32_t gi) { return ((gi >> 2) ^ (gi >> 3) ^ (gi >> 5)) & 1; }

__global__ void __launch_bounds__(1024, 1)
gn_kernel(const uint4* __restrict__ x, Scratch* __restrict__ scr, uint4* __restrict__ out,
          const uint2* __restrict__ g, const uint2* __restrict__ b, int never0, int never1, int never2) {
    __shared__ __align__(16) uint32_t s_ctl[4];
    __shared__ __align__(16) int s_race[4 * kND];
    __shared__ __align__(16) uint32_t s_red[64];

    uint4 v[8];
    uint2 g4, b4;
    uint32_t base;
    uint32_t tag = 0;
    const uint32_t t0 = tid_opaque();

    if (t0 < 128) {
        const uint32_t bid = blockIdx.x;
        if (bid >= 128) return;
        base = (7 * 128 + bid) * 1024 + (t0 & 96) * 8 + (t0 & 31);
        if (bid & 3) spin_until(clk(), (bid & 3) * kD0);
        load_chunk(v, g4, b4, base, x, g, b);
    } else {
        if (t0 >= 992) {
            const uint32_t start = clk(), bid = blockIdx.x, l = t0 & 31;
            const int G = gridDim.x;
            uint32_t info0 = 0, info = 0, tg = 0, side = 0, epoch = 0;
            if (l == 0) {
                char* pa = (char*)scr + opq(((bid >> 5) << 13) + ((bid & 32) << 7) + ((bid & 31) << 7));
                asm volatile("ld.volatile.global.u32 %0, [%2];\n ld.volatile.global.u32 %1, [%2+128];"
                             : "=r"(epoch), "=r"(info0) : "l"(&scr->epoch) : "memory");
                side = race_atom<true>(pa, (char*)((uintptr_t)pa ^ 4096)) > kThr ? 0 : 1;
                tg = epoch + 1;
                info = info0;
            }
            __syncwarp();
            if (bid == 0) {
                asm volatile("bar.sync 0, %0;" :: "n"(32 * (3 * kND + 1)) : "memory");
                if (l == 0 && (info0 & 3) != tg) {
                    uint32_t phase = 0, match = 0;
#pragma unroll
                    for (int p = 0; p < kND; p++) {
                        const int4 r = *(const int4*)&s_race[4 * p];
                        const bool xa = r.x > kThr, xb = r.y > kThr, oa = r.z > kThr, ob = r.w > kThr;
                        if (xa != xb && oa != ob && xa == oa) match |= 1u << p;
                        phase |= (uint32_t)(xb ^ (side != 0)) << p;
                    }
                    const uint32_t mine = tg | (match << 8) | (phase << 16);
                    asm volatile("atom.relaxed.gpu.global.cas.b32 %0, [%1], %2, %3;"
                                 : "=r"(info) : "l"(&scr->info), "r"(info0), "r"(mine) : "memory");
                    if (info == info0) info = mine;
                }
            }
            if (l == 0) {
                uint32_t old;
                asm volatile("atom.relaxed.gpu.global.add.u32 %0, [%1], %2;"
                             : "=r"(old) : "l"(&scr->claim), "r"(0x101u - side + (epoch >> 8)) : "memory");
                if ((info & 3) != tg)
                    asm volatile("ld.relaxed.gpu.global.u32 %0, [%1];" : "=r"(info) : "l"(&scr->info) : "memory");
                const int n = old >> 8, n0 = old & 0xff;
                if (n == G - 1)
                    asm volatile("st.relaxed.gpu.global.v2.u32 [%0], {%1,%2};"
                                 :: "l"(&scr->epoch), "r"(tg == 3 ? 0u : tg), "r"(0) : "memory");
                int rank = side ? n - n0 : n0;
                uint32_t cls = side;
                if (rank >= 64) {
                    cls ^= 1;
                    rank = 63 - (rank - (G - 64));
                    if (rank > 63) rank = 64;
                }
                s_ctl[1] = rank * 2 + cls;
                s_ctl[3] = side;
#pragma unroll 1
                for (int it = 0; (info & 3) != tg; it++) {
                    if (it < 4000) {
                        asm volatile("ld.relaxed.gpu.global.u32 %0, [%1];" : "=r"(info) : "l"(&scr->info) : "memory");
                    } else {
                        asm volatile("atom.relaxed.gpu.global.cas.b32 %0, [%1], %2, %3;"
                                     : "=r"(info) : "l"(&scr->info), "r"(info0), "r"(tg) : "memory");
                        if (info == info0 || it > 4016) info = tg;
                    }
                }
                const uint32_t match = info >> 8;
                uint32_t tab = 0, k = 0;
#pragma unroll
                for (int p = 0; p < kND; p++)
                    if ((match >> p) & 1) { tab |= (p | (k < kND - 1 ? 8u : 0u)) << (4 * k); k++; }
#pragma unroll
                for (int p = 0; p < kND; p++)
                    if (!((match >> p) & 1)) { tab |= p << (4 * k); k++; }
                s_ctl[0] = info;
                s_ctl[2] = tab;
            }
            __syncwarp();
            const uint32_t tab = s_ctl[2], rank = s_ctl[1] >> 1;
#pragma unroll 1
            for (int k = kNS; k < 8; k++) {
                const uint32_t ph = ((tab >> (4 * (k - kNS))) & 8) ? rank : bid;
                spin_until(start, kT1 + ((k - 1) * 4 + (ph & 3)) * kDT);
                if (k < 7) asm volatile("bar.arrive %0, 160;" :: "r"(k) : "memory");
            }
        } else if (t0 >= 960) {
            const uint32_t start = clk(), bid = blockIdx.x;
            if (bid < 128)
                asm volatile("st.relaxed.gpu.global.v4.u32 [%0], {%1,%1,%1,%1};"
                             :: "l"(boff(scr->slots, opq(bid * 512 + (t0 & 31) * 16))), "r"(0) : "memory");
#pragma unroll 1
            for (int k = 1; k < kNS; k++) {
                spin_until(start, kT1 + ((k - 1) * 4 + (bid & 3)) * kDT);
                asm volatile("bar.arrive %0, 160;" :: "r"(k) : "memory");
            }
        } else if (blockIdx.x == 0 && t0 - kNS * 128 < 3 * kND * 32) {
            const uint32_t q = (t0 >> 5) - kNS * 4;
            if ((t0 & 31) == 0) {
                if (q < kND) {
                    char* pa = (char*)out + opq(q << 21);
                    s_race[4 * q + 2] = race_atom<true>(pa, pa + 4096);
                    s_race[4 * q + 3] = race_atom<false>(pa + 4096, pa);
                } else {
                    const uint32_t u = q - kND;
                    const char* pa = (const char*)x + opq(((u >> 1) << 21) + (u & 1) * (4096 + 256));
                    s_race[4 * (u >> 1) + (u & 1)] = race_ld(pa, (const char*)((uintptr_t)pa ^ 4096));
                }
            }
            __syncwarp();
            asm volatile("bar.arrive 0, %0;" :: "n"(32 * (3 * kND + 1)) : "memory");
        }
        asm volatile("bar.sync %0, %1;" :: "r"(t0 >> 7), "r"(t0 < 896 ? 160 : 128) : "memory");

        const uint32_t t = tid_opaque(), bid = blockIdx.x;
        uint32_t page = 7 - (t >> 7), chunk = bid * 4 + ((t >> 5) & 3);
        bool active = bid < 128;
        if (t >= kNS * 128) {
            const uint4 ctl = *(const uint4*)s_ctl;
            const uint32_t ent = ctl.z >> (4 * ((t >> 7) - kNS));
            page = ent & 7;
            if (ent & 8) {
                tag = (ctl.x & 3) | (ctl.w << 2);
                active = ctl.y < 128;
                const uint32_t gi = (ctl.y & ~1u) + ((t >> 6) & 1);
                const uint32_t first = (ctl.y ^ (ctl.x >> (16 + page)) ^ group_class(gi)) & 1;
                chunk = gi * 4 + ((t & 32) ? 3 - first : first);
            }
        }
        if (!active) return;
        base = (chunk + page * 512) * 256 + (t & 31);
        load_chunk(v, g4, b4, base, x, g, b);
    }

    const uint32_t t = tid_opaque();
    const int l = t & 31;
    const uint32_t part = (__float_as_uint(warp_sums<8>(v, l)) & ~3u) | (tag & 3);
    bool ok = true;
    uint4 pa, pb;
    if (tag == 0) {
        if ((l & 15) == 0) s_red[(t >> 5) * 2 + (l >> 4)] = part;
        asm volatile("bar.sync %0, 128;" :: "r"((t >> 7) + 8) : "memory");
        pa = *(const uint4*)&s_red[(t >> 7) * 8];
        pb = *(const uint4*)&s_red[(t >> 7) * 8 + 4];
    } else {
        const uint32_t gr = base >> 10;
        const uint32_t so = ((gr >> 7) << 13) + ((((gr >> 7) ^ (tag >> 2) ^ 1) & 1) << 12) + (gr & 127) * 32;
        if ((l & 7) == 0)
            asm volatile("st.relaxed.gpu.global.u32 [%0], %1;"
                         :: "l"(boff(scr->slots, opq((so ^ ((~l & 8) << 9)) + ((base >> 8) & 3) * 8 + ((l >> 4) << 2)))),
                            "r"(part) : "memory");
        const uint4* sl = boff(scr->slots, opq(so));
        tag &= 3;
        ok = false;
#pragma unroll 1
        for (int it = 0; it < 4000; it++) {
            asm volatile("ld.relaxed.gpu.global.v4.u32 {%0,%1,%2,%3}, [%8];\n ld.relaxed.gpu.global.v4.u32 {%4,%5,%6,%7}, [%8+16];"
                         : "=r"(pa.x), "=r"(pa.y), "=r"(pa.z), "=r"(pa.w), "=r"(pb.x), "=r"(pb.y), "=r"(pb.z), "=r"(pb.w)
                         : "l"(sl) : "memory");
            const uint32_t all_and = pa.x & pa.y & pa.z & pa.w & pb.x & pb.y & pb.z & pb.w;
            const uint32_t all_or = pa.x | pa.y | pa.z | pa.w | pb.x | pb.y | pb.z | pb.w;
            if (__all_sync(0xffffffffu, (((all_and ^ tag) | (all_or ^ tag)) & 3) == 0)) { ok = true; break; }
        }
        pa.x &= ~3u; pa.y &= ~3u; pa.z &= ~3u; pa.w &= ~3u;
        pb.x &= ~3u; pb.y &= ~3u; pb.z &= ~3u; pb.w &= ~3u;
    }
    const float S = (__uint_as_float(pa.x) + __uint_as_float(pa.z)) + (__uint_as_float(pb.x) + __uint_as_float(pb.z));
    const float Q = (__uint_as_float(pa.y) + __uint_as_float(pa.w)) + (__uint_as_float(pb.y) + __uint_as_float(pb.w));
    const float mu = S * (1.f / kGroupElems);
    const float m2 = Q * (1.f / kGroupElems);
    const float var = fmaf(-mu, mu, m2);
    if (!ok || !(var * 64.f >= m2 && m2 < 3e38f)) {
        exact_path(x, (const unsigned short*)g, (const unsigned short*)b, out, base, 8);
        return;
    }
    const float rstd = rsqrtf(var + kEps);

    uint4* op = boff(out, opq(base << 4));
#pragma unroll
    for (int i = 0; i < 8; i++) {
        const uint32_t gw = (i >> 2) ? g4.y : g4.x, bw = (i >> 2) ? b4.y : b4.x;
        const float gf = ((i >> 1) & 1) ? bf_hi(gw) : bf_lo(gw), bf = ((i >> 1) & 1) ? bf_hi(bw) : bf_lo(bw);
        const float sc = gf * rstd, sh = fmaf(-mu, sc, bf);
        const uint4 o = norm4(v[i], sc, sh);
        asm volatile("st.global.v4.u32 [%0], {%1,%2,%3,%4};"
                     :: "l"(op + i * 32), "r"(o.x), "r"(o.y), "r"(o.z), "r"(o.w) : "memory");
        if (i == 1 && never0 < 0) asm volatile("exit;");
        if (i == 3 && never1 < 0) asm volatile("exit;");
        if (i == 5 && never2 < 0) asm volatile("exit;");
    }
}

__global__ void __launch_bounds__(256, 4)
gn_simple(const uint4* __restrict__ x, const __nv_bfloat16* __restrict__ g, const __nv_bfloat16* __restrict__ b,
          uint4* __restrict__ out) {
    __shared__ float red[2][8];
    const uint32_t t = threadIdx.x, w = t >> 5, l = t & 31;
    const uint32_t base = blockIdx.x * 1024 + w * 128 + l;
    uint4 v[4];
#pragma unroll
    for (int i = 0; i < 4; i++) v[i] = __ldg(x + base + i * 32);
    const float r = warp_sums<4>(v, l);
    if ((l & 15) == 0) red[l >> 4][w] = r;
    __syncthreads();
    float S = 0.f, Q = 0.f;
#pragma unroll
    for (int i = 0; i < 8; i++) { S += red[0][i]; Q += red[1][i]; }
    const float mu = S * (1.f / kGroupElems);
    const float m2 = Q * (1.f / kGroupElems);
    const float var = fmaf(-mu, mu, m2);
    if (!(var * 64.f >= m2 && m2 < 3e38f)) {
        exact_path(x, (const unsigned short*)g, (const unsigned short*)b, out, base, 4);
        return;
    }
    const float rstd = rsqrtf(var + kEps);
#pragma unroll
    for (int i = 0; i < 4; i++) {
        const int c = (blockIdx.x & 31) * 16 + w * 2 + (i >> 1);
        const float sc = __bfloat162float(g[c]) * rstd, sh = fmaf(-mu, sc, __bfloat162float(b[c]));
        out[base + i * 32] = norm4(v[i], sc, sh);
    }
}

}

extern "C" void kernel_launch(void* const* d_in, const int* in_sizes, int n_in, void* d_out, int out_size) {
    static int sms = 0;
    static Scratch* scr = nullptr;
    if (sms == 0) {
        int dev = 0;
        cudaGetDevice(&dev);
        cudaDeviceGetAttribute(&sms, cudaDevAttrMultiProcessorCount, dev);
        void* raw = nullptr;
        if (cudaGetSymbolAddress(&raw, g_scratch) == cudaSuccess)
            scr = (Scratch*)(((uintptr_t)raw + sizeof(Scratch) - 1) & ~(uintptr_t)(sizeof(Scratch) - 1));
    }
    const uint4* x = (const uint4*)d_in[0];
    uint4* out = (uint4*)d_out;
    const int ngroups = in_sizes[0] / kGroupElems;
    const bool paged = (((uintptr_t)x | (uintptr_t)out) & ((2u << 20) - 1)) == 0 &&
                       (((uintptr_t)d_in[1] | (uintptr_t)d_in[2]) & 7) == 0;
    if (ngroups == kNumGroups && paged && sms >= 128 && sms <= 160 && scr != nullptr) {
        gn_kernel<<<sms, 1024>>>(x, scr, out, (const uint2*)d_in[1], (const uint2*)d_in[2], 0, 0, 0);
    } else {
        gn_simple<<<ngroups, 256>>>(x, (const __nv_bfloat16*)d_in[1], (const __nv_bfloat16*)d_in[2], out);
    }
}
```

```cpp
#include <cuda_runtime.h>
#include <cuda_bf16.h>
#include <stdint.h>

namespace {

constexpr int kGroupElems = 8192;
constexpr int kNumGroups = 1024;
constexpr float kEps = 1e-5f;

constexpr int kNS = 3;
constexpr int kND = 8 - kNS;
constexpr int kT1 = 1200;
constexpr int kDT = 300;
constexpr int kD0 = 270;
constexpr int kProber = 3;
constexpr int kThr = 80;

struct Scratch {
    uint4 probe[2560];
    unsigned int epoch, claim, pad0[30];
    unsigned int info, pad1[31];
    unsigned int pad2[(65536 - 40960 - 256) / 4];
    uint4 slots[4096];
};
static_assert(sizeof(Scratch) == 131072, "scratch layout");
__device__ uint4 g_scratch[2 * sizeof(Scratch) / sizeof(uint4)];

__device__ __forceinline__ float bf_lo(uint32_t v) { return __uint_as_float(v << 16); }
__device__ __forceinline__ float bf_hi(uint32_t v) { return __uint_as_float(v & 0xffff0000u); }
__device__ __forceinline__ uint32_t pack_bf(float lo, float hi) {
    uint32_t r;
    asm("cvt.rn.bf16x2.f32 %0, %1, %2;" : "=r"(r) : "f"(hi), "f"(lo));
    return r;
}
__device__ __forceinline__ uint4 norm4(uint4 v, float sc, float sh) {
    uint4 o;
    o.x = pack_bf(fmaf(bf_lo(v.x), sc, sh), fmaf(bf_hi(v.x), sc, sh));
    o.y = pack_bf(fmaf(bf_lo(v.y), sc, sh), fmaf(bf_hi(v.y), sc, sh));
    o.z = pack_bf(fmaf(bf_lo(v.z), sc, sh), fmaf(bf_hi(v.z), sc, sh));
    o.w = pack_bf(fmaf(bf_lo(v.w), sc, sh), fmaf(bf_hi(v.w), sc, sh));
    return o;
}
__device__ __forceinline__ uint32_t clk() {
    uint32_t r;
    asm volatile("mov.u32 %0, %%clock;" : "=r"(r)::"memory");
    return r;
}
__device__ __forceinline__ uint32_t clk_after(uint32_t v) {
    uint32_t r;
    asm volatile("{ .reg .pred p; setp.eq.u32 p, %1, 0x7fc0dea1; @p mov.u32 %0, %%clock_hi; @!p mov.u32 %0, %%clock; }"
                 : "=r"(r) : "r"(v) : "memory");
    return r;
}
__device__ __forceinline__ uint32_t dep_zero(uint32_t v) { return v == 0x7fc0dea1u ? 4u : 0u; }
__device__ __forceinline__ void spin_until(uint32_t start, int cycles) {
    const uint32_t tgt = start + cycles;
    while ((int)(tgt - clk()) > 0) {}
}
__device__ __forceinline__ uint32_t tid_opaque() {
    uint32_t r;
    asm volatile("mov.u32 %0, %%tid.x;" : "=r"(r));
    return r;
}
__device__ __forceinline__ uint32_t opq(uint32_t v) {
    asm volatile("" : "+r"(v));
    return v;
}
template <typename T> __device__ __forceinline__ T* boff(T* p, uint32_t bytes) { return (T*)((char*)p + bytes); }
template <typename T> __device__ __forceinline__ const T* boff(const T* p, uint32_t bytes) { return (const T*)((const char*)p + bytes); }

__device__ __forceinline__ int race_ld(const char* pa, const char* pb) {
    uint32_t a0, b0, a1, b1;
    asm volatile("prefetch.global.L2 [%2];\n prefetch.global.L2 [%3];\n"
                 "ld.volatile.global.u32 %0, [%2];\n ld.volatile.global.u32 %1, [%3];"
                 : "=r"(a0), "=r"(b0) : "l"(pa), "l"(pb) : "memory");
    const uint32_t z = dep_zero(a0 ^ b0);
    asm volatile("ld.volatile.global.u32 %0, [%2+64];\n ld.volatile.global.u32 %1, [%3+64];"
                 : "=r"(a1), "=r"(b1) : "l"(pa + z), "l"(pb + z) : "memory");
    const uint32_t ta = clk_after(a1);
    const uint32_t tb = clk_after(b1);
    return (int)(tb - ta);
}
template <bool kFresh>
__device__ __forceinline__ int race_atom(char* pa, char* pb) {
    uint32_t a1, b1, z = 0;
    if (kFresh) {
        asm volatile("st.volatile.global.v4.u32 [%2], {%4,%4,%4,%4};\n st.volatile.global.v4.u32 [%2+16], {%4,%4,%4,%4};\n"
                     "st.volatile.global.v4.u32 [%3], {%4,%4,%4,%4};\n st.volatile.global.v4.u32 [%3+16], {%4,%4,%4,%4};\n"
                     "atom.relaxed.gpu.global.exch.b32 %0, [%2], 1;\n atom.relaxed.gpu.global.exch.b32 %1, [%3], 1;"
                     : "=r"(a1), "=r"(b1) : "l"(pa), "l"(pb), "r"(0) : "memory");
        z = dep_zero(a1 ^ b1);
    }
    asm volatile("atom.relaxed.gpu.global.exch.b32 %0, [%2+16], 2;\n atom.relaxed.gpu.global.exch.b32 %1, [%3+16], 2;"
                 : "=r"(a1), "=r"(b1) : "l"(pa + z), "l"(pb + z) : "memory");
    const uint32_t ta = clk_after(a1);
    const uint32_t tb = clk_after(b1);
    return (int)(tb - ta);
}

template <int NV>
__device__ __forceinline__ float warp_sums(const uint4 (&v)[NV], int lane) {
    float s0 = 0.f, s1 = 0.f, q0 = 0.f, q1 = 0.f;
#pragma unroll
    for (int i = 0; i < NV; i++) {
        const uint32_t wv[4] = {v[i].x, v[i].y, v[i].z, v[i].w};
#pragma unroll
        for (int j = 0; j < 4; j++) {
            const float a = bf_lo(wv[j]), c = bf_hi(wv[j]);
            s0 += a; s1 += c;
            q0 = fmaf(a, a, q0); q1 = fmaf(c, c, q1);
        }
    }
    const float s = s0 + s1, q = q0 + q1;
    const bool lo = lane < 16;
    float r = (lo ? s : q) + __shfl_xor_sync(0xffffffffu, lo ? q : s, 16);
    r += __shfl_xor_sync(0xffffffffu, r, 8);
    r += __shfl_xor_sync(0xffffffffu, r, 4);
    r += __shfl_xor_sync(0xffffffffu, r, 2);
    r += __shfl_xor_sync(0xffffffffu, r, 1);
    return r;
}

__device__ __noinline__ void exact_path(const uint4* __restrict__ x, const unsigned short* __restrict__ g,
                                        const unsigned short* __restrict__ b, uint4* __restrict__ out,
                                        uint32_t base, int nv) {
    const uint4* xg = x + (base & ~1023u) + (base & 31);
    float s = 0.f;
#pragma unroll 4
    for (int i = 0; i < 32; i++) {
        const uint4 u = __ldg(xg + i * 32);
        s += ((bf_lo(u.x) + bf_hi(u.x)) + (bf_lo(u.y) + bf_hi(u.y))) + ((bf_lo(u.z) + bf_hi(u.z)) + (bf_lo(u.w) + bf_hi(u.w)));
    }
#pragma unroll 1
    for (int o = 16; o > 0; o >>= 1) s += __shfl_xor_sync(0xffffffffu, s, o);
    const float mu = s * (1.f / kGroupElems);
    float a = 0.f;
#pragma unroll 4
    for (int i = 0; i < 32; i++) {
        const uint4 u = __ldg(xg + i * 32);
        const uint32_t wv[4] = {u.x, u.y, u.z, u.w};
#pragma unroll
        for (int j = 0; j < 4; j++) {
            const float d0 = bf_lo(wv[j]) - mu, d1 = bf_hi(wv[j]) - mu;
            a = fmaf(d0, d0, a);
            a = fmaf(d1, d1, a);
        }
    }
#pragma unroll 1
    for (int o = 16; o > 0; o >>= 1) a += __shfl_xor_sync(0xffffffffu, a, o);
    const float rstd = rsqrtf(a * (1.f / kGroupElems) + kEps);
#pragma unroll 1
    for (int i = 0; i < nv; i++) {
        const uint32_t k = base + i * 32, c = (k >> 6) & 511;
        const uint4 u = __ldg(x + k);
        const float sc = bf_lo(g[c]) * rstd, sh = bf_lo(b[c]);
        uint4 o;
        o.x = pack_bf(fmaf(bf_lo(u.x) - mu, sc, sh), fmaf(bf_hi(u.x) - mu, sc, sh));
        o.y = pack_bf(fmaf(bf_lo(u.y) - mu, sc, sh), fmaf(bf_hi(u.y) - mu, sc, sh));
        o.z = pack_bf(fmaf(bf_lo(u.z) - mu, sc, sh), fmaf(bf_hi(u.z) - mu, sc, sh));
        o.w = pack_bf(fmaf(bf_lo(u.w) - mu, sc, sh), fmaf(bf_hi(u.w) - mu, sc, sh));
        out[k] = o;
    }
}

__device__ __forceinline__ void load_chunk(uint4 (&v)[8], uint2& g4, uint2& b4, uint32_t base,
                                           const uint4* x, const uint2* g, const uint2* b) {
    const uint4* xp = boff(x, opq(base << 4));
    const uint32_t go = opq((base >> 5) & 0x3f8);
#pragma unroll
    for (int i = 0; i < 8; i++)
        asm volatile("ld.global.nc.L1::no_allocate.v4.u32 {%0,%1,%2,%3}, [%4];"
                     : "=r"(v[i].x), "=r"(v[i].y), "=r"(v[i].z), "=r"(v[i].w) : "l"(xp + i * 32));
    asm volatile("ld.global.nc.v2.u32 {%0,%1}, [%2];" : "=r"(g4.x), "=r"(g4.y) : "l"(boff(g, go)));
    asm volatile("ld.global.nc.v2.u32 {%0,%1}, [%2];" : "=r"(b4.x), "=r"(b4.y) : "l"(boff(b, go)));
}

__host__ __device__ constexpr uint32_t group_class(uint32_t gi) { return ((gi >> 2) ^ (gi >> 3) ^ (gi >> 5)) & 1; }
__host__ __device__ constexpr uint32_t own_group(uint32_t bid) { return ((bid & 3) << 5) | ((bid & 127) >> 2); }

__global__ void __launch_bounds__(1024, 1)
gn_kernel(const uint4* __restrict__ x, Scratch* __restrict__ scr, uint4* __restrict__ out,
          const uint2* __restrict__ g, const uint2* __restrict__ b, int never0, int never1, int never2) {
    __shared__ __align__(16) uint32_t s_ctl[4];
    __shared__ __align__(16) int s_race[4 * kND];
    __shared__ __align__(16) uint32_t s_red[64];

    uint4 v[8];
    uint2 g4, b4;
    uint32_t base;
    uint32_t tag = 0;
    const uint32_t t0 = tid_opaque();

    if (t0 < 128) {
        const uint32_t bid = blockIdx.x;
        if (bid >= 128) return;
        base = (7 * 128 + own_group(bid)) * 1024 + (t0 & 96) * 8 + (t0 & 31);
        if (bid & 3) spin_until(clk(), (bid & 3) * kD0);
        load_chunk(v, g4, b4, base, x, g, b);
    } else {
        if (t0 >= 992) {
            const uint32_t start = clk(), bid = blockIdx.x, l = t0 & 31;
            const int G = gridDim.x;
            uint32_t info0 = 0, info = 0, tg = 0, side = 0, epoch = 0;
            if (l == 0) {
                char* pa = (char*)scr + opq(((bid >> 5) << 13) + ((bid & 32) << 7) + ((bid & 31) << 7));
                asm volatile("ld.volatile.global.u32 %0, [%2];\n ld.volatile.global.u32 %1, [%2+128];"
                             : "=r"(epoch), "=r"(info0) : "l"(&scr->epoch) : "memory");
                side = race_atom<true>(pa, (char*)((uintptr_t)pa ^ 4096)) > kThr ? 0 : 1;
                tg = epoch + 1;
                info = info0;
            }
            __syncwarp();
            if (bid == kProber) {
                asm volatile("bar.sync 0, %0;" :: "n"(32 * (3 * kND + 1)) : "memory");
                if (l == 0 && (info0 & 3) != tg) {
                    uint32_t phase = 0, match = 0;
#pragma unroll
                    for (int p = 0; p < kND; p++) {
                        const int4 r = *(const int4*)&s_race[4 * p];
                        const bool xa = r.x > kThr, xb = r.y > kThr, oa = r.z > kThr, ob = r.w > kThr;
                        if (xa != xb && oa != ob && xa == oa) match |= 1u << p;
                        phase |= (uint32_t)(xb ^ (side != 0)) << p;
                    }
                    const uint32_t mine = tg | (match << 8) | (phase << 16);
                    asm volatile("atom.relaxed.gpu.global.cas.b32 %0, [%1], %2, %3;"
                                 : "=r"(info) : "l"(&scr->info), "r"(info0), "r"(mine) : "memory");
                    if (info == info0) info = mine;
                }
            }
            if (l == 0) {
                uint32_t old;
                asm volatile("atom.relaxed.gpu.global.add.u32 %0, [%1], %2;"
                             : "=r"(old) : "l"(&scr->claim), "r"(0x101u - side + (epoch >> 8)) : "memory");
                if ((info & 3) != tg)
                    asm volatile("ld.relaxed.gpu.global.u32 %0, [%1];" : "=r"(info) : "l"(&scr->info) : "memory");
                const int n = old >> 8, n0 = old & 0xff;
                if (n == G - 1)
                    asm volatile("st.relaxed.gpu.global.v2.u32 [%0], {%1,%2};"
                                 :: "l"(&scr->epoch), "r"(tg == 3 ? 0u : tg), "r"(0) : "memory");
                int rank = side ? n - n0 : n0;
                uint32_t cls = side;
                if (rank >= 64) {
                    cls ^= 1;
                    rank = 63 - (rank - (G - 64));
                    if (rank > 63) rank = 64;
                }
                s_ctl[1] = rank * 2 + cls;
                s_ctl[3] = side;
#pragma unroll 1
                for (int it = 0; (info & 3) != tg; it++) {
                    if (it < 4000) {
                        asm volatile("ld.relaxed.gpu.global.u32 %0, [%1];" : "=r"(info) : "l"(&scr->info) : "memory");
                    } else {
                        asm volatile("atom.relaxed.gpu.global.cas.b32 %0, [%1], %2, %3;"
                                     : "=r"(info) : "l"(&scr->info), "r"(info0), "r"(tg) : "memory");
                        if (info == info0 || it > 4016) info = tg;
                    }
                }
                const uint32_t match = info >> 8;
                uint32_t tab = 0, k = 0;
#pragma unroll
                for (int p = 0; p < kND; p++)
                    if ((match >> p) & 1) { tab |= (p | (k < kND - 1 ? 8u : 0u)) << (4 * k); k++; }
#pragma unroll
                for (int p = 0; p < kND; p++)
                    if (!((match >> p) & 1)) { tab |= p << (4 * k); k++; }
                s_ctl[0] = info;
                s_ctl[2] = tab;
            }
            __syncwarp();
            const uint32_t tab = s_ctl[2], rank = s_ctl[1] >> 1;
#pragma unroll 1
            for (int k = kNS; k < 8; k++) {
                const uint32_t ph = ((tab >> (4 * (k - kNS))) & 8) ? rank : bid;
                spin_until(start, kT1 + ((k - 1) * 4 + (ph & 3)) * kDT);
                if (k < 7) asm volatile("bar.arrive %0, 160;" :: "r"(k) : "memory");
            }
        } else if (t0 >= 960) {
            const uint32_t start = clk(), bid = blockIdx.x;
            if (bid < 128)
                asm volatile("st.relaxed.gpu.global.v4.u32 [%0], {%1,%1,%1,%1};"
                             :: "l"(boff(scr->slots, opq(bid * 512 + (t0 & 31) * 16))), "r"(0) : "memory");
#pragma unroll 1
            for (int k = 1; k < kNS; k++) {
                spin_until(start, kT1 + ((k - 1) * 4 + (bid & 3)) * kDT);
                asm volatile("bar.arrive %0, 160;" :: "r"(k) : "memory");
            }
        } else if (blockIdx.x == kProber && t0 - kNS * 128 < 3 * kND * 32) {
            constexpr uint32_t grp = own_group(kProber), flip = group_class(grp);
            const uint32_t q = (t0 >> 5) - kNS * 4;
            if ((t0 & 31) == 0) {
                if (q < kND) {
                    char* pa = (char*)out + opq((q << 21) + grp * 16384);
                    s_race[4 * q + 2 + flip] = race_atom<true>(pa, pa + 4096);
                    s_race[4 * q + 3 - flip] = race_atom<false>(pa + 4096, pa);
                } else {
                    const uint32_t u = q - kND;
                    const char* pa = (const char*)x + opq(((u >> 1) << 21) + (u & 1) * (4096 + 256));
                    s_race[4 * (u >> 1) + (u & 1)] = race_ld(pa, (const char*)((uintptr_t)pa ^ 4096));
                }
            }
            __syncwarp();
            asm volatile("bar.arrive 0, %0;" :: "n"(32 * (3 * kND + 1)) : "memory");
        }
        asm volatile("bar.sync %0, %1;" :: "r"(t0 >> 7), "r"(t0 < 896 ? 160 : 128) : "memory");

        const uint32_t t = tid_opaque(), bid = blockIdx.x;
        uint32_t page = 7 - (t >> 7), chunk = own_group(bid) * 4 + ((t >> 5) & 3);
        bool active = bid < 128;
        if (t >= kNS * 128) {
            const uint4 ctl = *(const uint4*)s_ctl;
            const uint32_t ent = ctl.z >> (4 * ((t >> 7) - kNS));
            page = ent & 7;
            if (ent & 8) {
                tag = (ctl.x & 3) | (ctl.w << 2);
                active = ctl.y < 128;
                const uint32_t gi = ((ctl.y & 6) << 4) | ((ctl.y >> 2) & 30) | ((t >> 6) & 1);
                const uint32_t first = (ctl.y ^ (ctl.x >> (16 + page)) ^ group_class(gi)) & 1;
                chunk = gi * 4 + ((t & 32) ? 3 - first : first);
            }
        }
        if (!active) return;
        base = (chunk + page * 512) * 256 + (t & 31);
        load_chunk(v, g4, b4, base, x, g, b);
    }

    const uint32_t t = tid_opaque();
    const int l = t & 31;
    const uint32_t part = (__float_as_uint(warp_sums<8>(v, l)) & ~3u) | (tag & 3);
    bool ok = true;
    uint4 pa, pb;
    if (tag == 0) {
        if ((l & 15) == 0) s_red[(t >> 5) * 2 + (l >> 4)] = part;
        asm volatile("bar.sync %0, 128;" :: "r"((t >> 7) + 8) : "memory");
        pa = *(const uint4*)&s_red[(t >> 7) * 8];
        pb = *(const uint4*)&s_red[(t >> 7) * 8 + 4];
    } else {
        const uint32_t gr = base >> 10;
        const uint32_t so = ((gr >> 7) << 13) + ((((gr >> 7) ^ (tag >> 2) ^ 1) & 1) << 12) + (gr & 127) * 32;
        if ((l & 7) == 0)
            asm volatile("st.relaxed.gpu.global.u32 [%0], %1;"
                         :: "l"(boff(scr->slots, opq((so ^ ((~l & 8) << 9)) + ((base >> 8) & 3) * 8 + ((l >> 4) << 2)))),
                            "r"(part) : "memory");
        const uint4* sl = boff(scr->slots, opq(so));
        tag &= 3;
        ok = false;
#pragma unroll 1
        for (int it = 0; it < 4000; it++) {
            asm volatile("ld.relaxed.gpu.global.v4.u32 {%0,%1,%2,%3}, [%8];\n ld.relaxed.gpu.global.v4.u32 {%4,%5,%6,%7}, [%8+16];"
                         : "=r"(pa.x), "=r"(pa.y), "=r"(pa.z), "=r"(pa.w), "=r"(pb.x), "=r"(pb.y), "=r"(pb.z), "=r"(pb.w)
                         : "l"(sl) : "memory");
            const uint32_t all_and = pa.x & pa.y & pa.z & pa.w & pb.x & pb.y & pb.z & pb.w;
            const uint32_t all_or = pa.x | pa.y | pa.z | pa.w | pb.x | pb.y | pb.z | pb.w;
            if (__all_sync(0xffffffffu, (((all_and ^ tag) | (all_or ^ tag)) & 3) == 0)) { ok = true; break; }
        }
        pa.x &= ~3u; pa.y &= ~3u; pa.z &= ~3u; pa.w &= ~3u;
        pb.x &= ~3u; pb.y &= ~3u; pb.z &= ~3u; pb.w &= ~3u;
    }
    const float S = (__uint_as_float(pa.x) + __uint_as_float(pa.z)) + (__uint_as_float(pb.x) + __uint_as_float(pb.z));
    const float Q = (__uint_as_float(pa.y) + __uint_as_float(pa.w)) + (__uint_as_float(pb.y) + __uint_as_float(pb.w));
    const float mu = S * (1.f / kGroupElems);
    const float m2 = Q * (1.f / kGroupElems);
    const float var = fmaf(-mu, mu, m2);
    if (!ok || !(var * 64.f >= m2 && m2 < 3e38f)) {
        exact_path(x, (const unsigned short*)g, (const unsigned short*)b, out, base, 8);
        return;
    }
    const float rstd = rsqrtf(var + kEps);

    uint4* op = boff(out, opq(base << 4));
#pragma unroll
    for (int i = 0; i < 8; i++) {
        const uint32_t gw = (i >> 2) ? g4.y : g4.x, bw = (i >> 2) ? b4.y : b4.x;
        const float gf = ((i >> 1) & 1) ? bf_hi(gw) : bf_lo(gw), bf = ((i >> 1) & 1) ? bf_hi(bw) : bf_lo(bw);
        const float sc = gf * rstd, sh = fmaf(-mu, sc, bf);
        const uint4 o = norm4(v[i], sc, sh);
        asm volatile("st.global.v4.u32 [%0], {%1,%2,%3,%4};"
                     :: "l"(op + i * 32), "r"(o.x), "r"(o.y), "r"(o.z), "r"(o.w) : "memory");
        if (i == 1 && never0 < 0) asm volatile("exit;");
        if (i == 3 && never1 < 0) asm volatile("exit;");
        if (i == 5 && never2 < 0) asm volatile("exit;");
    }
}

__global__ void __launch_bounds__(256, 4)
gn_simple(const uint4* __restrict__ x, const __nv_bfloat16* __restrict__ g, const __nv_bfloat16* __restrict__ b,
          uint4* __restrict__ out) {
    __shared__ float red[2][8];
    const uint32_t t = threadIdx.x, w = t >> 5, l = t & 31;
    const uint32_t base = blockIdx.x * 1024 + w * 128 + l;
    uint4 v[4];
#pragma unroll
    for (int i = 0; i < 4; i++) v[i] = __ldg(x + base + i * 32);
    const float r = warp_sums<4>(v, l);
    if ((l & 15) == 0) red[l >> 4][w] = r;
    __syncthreads();
    float S = 0.f, Q = 0.f;
#pragma unroll
    for (int i = 0; i < 8; i++) { S += red[0][i]; Q += red[1][i]; }
    const float mu = S * (1.f / kGroupElems);
    const float m2 = Q * (1.f / kGroupElems);
    const float var = fmaf(-mu, mu, m2);
    if (!(var * 64.f >= m2 && m2 < 3e38f)) {
        exact_path(x, (const unsigned short*)g, (const unsigned short*)b, out, base, 4);
        return;
    }
    const float rstd = rsqrtf(var + kEps);
#pragma unroll
    for (int i = 0; i < 4; i++) {
        const int c = (blockIdx.x & 31) * 16 + w * 2 + (i >> 1);
        const float sc = __bfloat162float(g[c]) * rstd, sh = fmaf(-mu, sc, __bfloat162float(b[c]));
        out[base + i * 32] = norm4(v[i], sc, sh);
    }
}

}

extern "C" void kernel_launch(void* const* d_in, const int* in_sizes, int n_in, void* d_out, int out_size) {
    static int sms = 0;
    static Scratch* scr = nullptr;
    if (sms == 0) {
        int dev = 0;
        cudaGetDevice(&dev);
        cudaDeviceGetAttribute(&sms, cudaDevAttrMultiProcessorCount, dev);
        void* raw = nullptr;
        if (cudaGetSymbolAddress(&raw, g_scratch) == cudaSuccess)
            scr = (Scratch*)(((uintptr_t)raw + sizeof(Scratch) - 1) & ~(uintptr_t)(sizeof(Scratch) - 1));
    }
    const uint4* x = (const uint4*)d_in[0];
    uint4* out = (uint4*)d_out;
    const int ngroups = in_sizes[0] / kGroupElems;
    const bool paged = (((uintptr_t)x | (uintptr_t)out) & ((2u << 20) - 1)) == 0 &&
                       (((uintptr_t)d_in[1] | (uintptr_t)d_in[2]) & 7) == 0;
    if (ngroups == kNumGroups && paged && sms >= 128 && sms <= 160 && scr != nullptr) {
        gn_kernel<<<sms, 1024>>>(x, scr, out, (const uint2*)d_in[1], (const uint2*)d_in[2], 0, 0, 0);
    } else {
        gn_simple<<<ngroups, 256>>>(x, (const __nv_bfloat16*)d_in[1], (const __nv_bfloat16*)d_in[2], out);
    }
}
```
